```python
import torch

def _softmax(x, axis=-1):
    return torch.softmax(x, dim=axis)
def _gelu(x):
    return torch.nn.functional.gelu(x, approximate="tanh")
def _silu(x):
    return torch.nn.functional.silu(x)
def _sigmoid(x):
    return torch.sigmoid(x)
def _layernorm(x, axis=-1, eps=1e-5):
    m = x.mean(dim=axis, keepdim=True)
    v = x.var(dim=axis, keepdim=True, unbiased=False)
    return (x - m) / torch.sqrt(v + eps)
def _scatter_add(tgt, idx, src, axis=0):
    return tgt.clone().index_add_(axis, idx, src)
def _segment_sum(src, seg, n):
    out = torch.zeros((n,) + src.shape[1:], dtype=src.dtype)
    return out.index_add_(0, seg, src)
def _pad(x, pw):
    flat = tuple(v for pair in reversed(pw) for v in pair)
    return torch.nn.functional.pad(x, flat)

kernel_name = 'parallel_sum__softmax_full_mha__glu_gated_reglu__prompt'

def setup_inputs():

    _w = (lambda a: (lambda t: t.to(torch.bfloat16) if t.is_floating_point() else t)(torch.as_tensor(a)))
    def _A_setup():
        B, S, D = 1, 2048, 512
        return {
            "x": _w((lambda *s: torch.randn(*s, dtype=torch.bfloat16) * 0.05)(B, S, D)),
            "wqkv": _w((lambda *s: torch.randn(*s, dtype=torch.bfloat16) * 0.05)(D, 3 * D)),
            "wo": _w((lambda *s: torch.randn(*s, dtype=torch.bfloat16) * 0.05)(D, D)),
        }
    _A_in = _A_setup()

    def _B_setup():
        B, S, D, F = 1, 2048, 512, 1376
        return {
            "x": _w((lambda *s: torch.randn(*s, dtype=torch.bfloat16) * 0.05)(B, S, D)),
            "W_gate": _w((lambda *s: torch.randn(*s, dtype=torch.bfloat16) * 0.4)(D, F) * (2.0 / D) ** 0.5),
            "W_up": _w((lambda *s: torch.randn(*s, dtype=torch.bfloat16) * 0.4)(D, F) * (2.0 / D) ** 0.5),
            "W_down": _w((lambda *s: torch.randn(*s, dtype=torch.bfloat16) * 0.4)(F, D) * (1.0 / F) ** 0.5),
        }
    _B_in = _B_setup()

    return {
        "A_x": _A_in["x"],
        "A_wqkv": _A_in["wqkv"],
        "A_wo": _A_in["wo"],
        "B_x": _B_in["x"],
        "B_W_gate": _B_in["W_gate"],
        "B_W_up": _B_in["W_up"],
        "B_W_down": _B_in["W_down"],
    }

def reference(A_x, A_wqkv, A_wo, B_x, B_W_gate, B_W_up, B_W_down):
    def _A_ref(x, wqkv, wo):
        B, S, D = x.shape
        H = 32; Dh = D // H
        qkv = (lambda x, *d: x.permute(*d))((x @ wqkv).reshape(B, S, 3, H, Dh), 2, 0, 3, 1, 4)
        q, k, v = qkv[0], qkv[1], qkv[2]
        scale = Dh ** -0.5
        scores = torch.einsum("bhqd,bhkd->bhqk", q, k) * scale
        p = _softmax(scores, axis=-1)
        o = torch.einsum("bhqk,bhkd->bhqd", p, v)
        return (lambda x, *d: x.permute(*d))(o, 0, 2, 1, 3).reshape(B, S, D) @ wo

    def _B_ref(x, W_gate, W_up, W_down):
        gate = torch.einsum("bsd,df->bsf", x, W_gate)
        up = torch.einsum("bsd,df->bsf", x, W_up)
        gate = gate * (lambda x, dt: x.to(dt))(gate > 0, gate.dtype)
        h = gate * up
        return torch.einsum("bsf,fd->bsd", h, W_down)

    x = A_x
    xn = _layernorm(x, axis=-1)
    return x + _A_ref(xn, A_wqkv, A_wo) + _B_ref(xn, B_W_gate, B_W_up, B_W_down)
```

```cpp
#include <cuda_runtime.h>
#include <cuda_bf16.h>
#include <cuda.h>
#include <stdint.h>

#define FFN_DELAY 0
#define MAGIC_BIAS 0x00003B80u
#define MB_LBO 128
namespace {

constexpr int S_ = 2048, D_ = 512, H_ = 32, F_ = 1376;
constexpr float QSCALE = 0.25f * 1.4426950408889634f;

__device__ __align__(1024) __nv_bfloat16 g_xn[S_ * D_];
__device__ __align__(1024) uint8_t g_q[H_ * 65536];
__device__ __align__(1024) uint8_t g_kv[H_ * 131072];
__device__ __align__(256) uint32_t g_nrm[8 * 16 * 64];
__device__ __align__(1024) __nv_bfloat16 g_h[S_ * F_];
__device__ __align__(1024) __nv_bfloat16 g_o[S_ * D_];
__device__ __align__(128) float2 g_stats[S_];
__device__ __align__(128) float g_csp[8 * 16 * 192];
struct Flags { unsigned int ln[16], cs[8], qkv[8], h[16], o[32]; };
__device__ unsigned int g_epoch;
__device__ Flags g_flags;
__device__ __align__(1024) float4 g_part[256 * 2 * 3 * 128];

#define TS_MIN(k)
#define TS_MAX(k)
#define TS_BOTH(k)
__device__ __forceinline__ uint32_t smem_u32(const void* p) { return (uint32_t)__cvta_generic_to_shared(p); }
__device__ __forceinline__ void mbar_init(uint32_t bar, uint32_t cnt) { asm volatile("mbarrier.init.shared::cta.b64 [%0], %1;" :: "r"(bar), "r"(cnt)); }
__device__ __forceinline__ void mbar_expect_tx(uint32_t bar, uint32_t bytes) { asm volatile("mbarrier.arrive.expect_tx.shared::cta.b64 _, [%0], %1;" :: "r"(bar), "r"(bytes) : "memory"); }
__device__ __forceinline__ void mbar_arrive(uint32_t bar) { asm volatile("mbarrier.arrive.shared::cta.b64 _, [%0];" :: "r"(bar) : "memory"); }
__device__ __forceinline__ bool mbar_try(uint32_t bar, uint32_t parity) {
    uint32_t ok;
    asm volatile("{\n.reg .pred p;\nmbarrier.try_wait.parity.shared::cta.b64 p, [%1], %2;\nselp.u32 %0, 1, 0, p;\n}" : "=r"(ok) : "r"(bar), "r"(parity) : "memory");
    return ok;
}
__device__ __forceinline__ void mbar_wait(uint32_t bar, uint32_t parity) {
    if (mbar_try(bar, parity)) return;
    #pragma unroll 1
    for (int it = 0; it < (1 << 20); it++) { if (mbar_try(bar, parity)) return; }
    __trap();
}
__device__ __forceinline__ void mbar_wait_cluster(uint32_t bar, uint32_t parity) {
    #pragma unroll 1
    for (int it = 0; it < (1 << 20); it++) {
        uint32_t ok;
        asm volatile("{\n.reg .pred p;\nmbarrier.try_wait.parity.relaxed.cluster.shared::cta.b64 p, [%1], %2;\nselp.u32 %0, 1, 0, p;\n}" : "=r"(ok) : "r"(bar), "r"(parity) : "memory");
        if (ok) return;
    }
    __trap();
}
__device__ __forceinline__ void bulk_load(uint32_t dst, const void* src, uint32_t bytes, uint32_t bar) {
    asm volatile("cp.async.bulk.shared::cluster.global.mbarrier::complete_tx::bytes [%0], [%1], %2, [%3];" :: "r"(dst), "l"(src), "r"(bytes), "r"(bar) : "memory");
}
__device__ __forceinline__ void bulk_load_mc(uint32_t dst, const void* src, uint32_t bytes, uint32_t bar, uint16_t mask) {
    asm volatile("cp.async.bulk.shared::cluster.global.mbarrier::complete_tx::bytes.multicast::cluster [%0], [%1], %2, [%3], %4;" :: "r"(dst), "l"(src), "r"(bytes), "r"(bar), "h"(mask) : "memory");
}
__device__ __forceinline__ void tma2d(uint32_t dst, const CUtensorMap* m, int c0, int c1, uint32_t bar) {
    asm volatile("cp.async.bulk.tensor.2d.shared::cluster.global.mbarrier::complete_tx::bytes [%0], [%1, {%3, %4}], [%2];" :: "r"(dst), "l"(m), "r"(bar), "r"(c0), "r"(c1) : "memory");
}
__device__ __forceinline__ void tma2d_store(const CUtensorMap* m, uint32_t src, int c0, int c1) {
    asm volatile("cp.async.bulk.tensor.2d.global.shared::cta.bulk_group [%0, {%2, %3}], [%1];" :: "l"(m), "r"(src), "r"(c0), "r"(c1) : "memory");
}
__device__ __forceinline__ void bar_sync(int id, int n) { asm volatile("bar.sync %0, %1;" :: "r"(id), "r"(n) : "memory"); }
__device__ __forceinline__ void bar_arrive(int id, int n) { asm volatile("bar.arrive %0, %1;" :: "r"(id), "r"(n) : "memory"); }
__device__ __forceinline__ void fence_async() { asm volatile("fence.proxy.async.global;" ::: "memory"); }
__device__ __forceinline__ void fence_async_smem() { asm volatile("fence.proxy.async.shared::cta;" ::: "memory"); }
__device__ __forceinline__ void flag_add(unsigned int* p) { asm volatile("red.release.gpu.global.add.u32 [%0], 1;" :: "l"(p) : "memory"); }
__device__ __forceinline__ void flag_add_relaxed(unsigned int* p) { asm volatile("red.relaxed.gpu.global.add.u32 [%0], 1;" :: "l"(p) : "memory"); }
__device__ __forceinline__ void flag_wait(const unsigned int* p, unsigned int target) {
    #pragma unroll 1
    for (int it = 0; it < (1 << 18); it++) {
        unsigned int v;
        asm volatile("ld.acquire.gpu.global.u32 %0, [%1];" : "=r"(v) : "l"(p) : "memory");
        if ((int)(v - target) >= 0) return;
        __nanosleep(40);
    }
    __trap();
}
__device__ __forceinline__ void stsm4(uint32_t addr, uint32_t r0, uint32_t r1, uint32_t r2, uint32_t r3) {
    asm volatile("stmatrix.sync.aligned.m8n8.x4.shared.b16 [%0], {%1,%2,%3,%4};" :: "r"(addr), "r"(r0), "r"(r1), "r"(r2), "r"(r3) : "memory");
}
__device__ __forceinline__ void tma2d_mc(uint32_t dst, const CUtensorMap* m, int c0, int c1, uint32_t bar, uint16_t mask) {
    asm volatile("cp.async.bulk.tensor.2d.shared::cluster.global.mbarrier::complete_tx::bytes.multicast::cluster [%0], [%1, {%3, %4}], [%2], %5;"
                 :: "r"(dst), "l"(m), "r"(bar), "r"(c0), "r"(c1), "h"(mask) : "memory");
}
__device__ __forceinline__ void tma3d(uint32_t dst, const CUtensorMap* m, int c0, int c1, int c2, uint32_t bar) {
    asm volatile("cp.async.bulk.tensor.3d.shared::cluster.global.mbarrier::complete_tx::bytes [%0], [%1, {%3, %4, %5}], [%2];"
                 :: "r"(dst), "l"(m), "r"(bar), "r"(c0), "r"(c1), "r"(c2) : "memory");
}
__device__ __forceinline__ void bulk_store(void* dst, uint32_t src, uint32_t bytes) {
    asm volatile("cp.async.bulk.global.shared::cta.bulk_group [%0], [%1], %2;" :: "l"(dst), "r"(src), "r"(bytes) : "memory");
}
__device__ __forceinline__ void tma3d_mc(uint32_t dst, const CUtensorMap* m, int c0, int c1, int c2, uint32_t bar, uint16_t mask) {
    asm volatile("cp.async.bulk.tensor.3d.shared::cluster.global.mbarrier::complete_tx::bytes.multicast::cluster [%0], [%1, {%3, %4, %5}], [%2], %6;"
                 :: "r"(dst), "l"(m), "r"(bar), "r"(c0), "r"(c1), "r"(c2), "h"(mask) : "memory");
}
__device__ __forceinline__ void l2_prefetch(const void* p, uint32_t bytes) { asm volatile("cp.async.bulk.prefetch.L2.global [%0], %1;" :: "l"(p), "r"(bytes) : "memory"); }
__device__ __forceinline__ bool mbar_test(uint32_t bar, uint32_t parity) {
    uint32_t ok;
    asm volatile("{\n.reg .pred p;\nmbarrier.test_wait.parity.relaxed.cluster.shared::cta.b64 p, [%1], %2;\nselp.u32 %0, 1, 0, p;\n}" : "=r"(ok) : "r"(bar), "r"(parity) : "memory");
    return ok;
}
__device__ __forceinline__ void mbar_arrive_remote(uint32_t bar, uint32_t cta) {
    asm volatile("{\n.reg .b32 ra;\nmapa.shared::cluster.u32 ra, %0, %1;\nmbarrier.arrive.relaxed.cluster.shared::cluster.b64 _, [ra];\n}" :: "r"(bar), "r"(cta) : "memory");
}
__device__ __forceinline__ void arrive_pair(uint32_t bar) { mbar_arrive_remote(bar, 0); mbar_arrive_remote(bar, 1); }
__device__ __forceinline__ int opaque_tid() { int t; asm volatile("mov.u32 %0, %%tid.x;" : "=r"(t)); return t; }
__device__ __forceinline__ bool elect_one() {
    uint32_t p;
    asm volatile("{\n.reg .pred p;\nelect.sync _|p, 0xffffffff;\nselp.u32 %0, 1, 0, p;\n}" : "=r"(p));
    return p;
}
__device__ __forceinline__ uint64_t make_desc(uint32_t saddr, uint32_t lbo, uint32_t sbo, uint32_t layout) {
    return (uint64_t)((saddr >> 4) & 0x3FFF) | ((uint64_t)((lbo >> 4) & 0x3FFF) << 16) | ((uint64_t)((sbo >> 4) & 0x3FFF) << 32) | ((uint64_t)layout << 62);
}
__device__ __forceinline__ void wg_fence() { asm volatile("wgmma.fence.sync.aligned;" ::: "memory"); }
__device__ __forceinline__ void wg_commit() { asm volatile("wgmma.commit_group.sync.aligned;" ::: "memory"); }
template<int N> __device__ __forceinline__ void wg_wait() { asm volatile("wgmma.wait_group.sync.aligned %0;" :: "n"(N) : "memory"); }
template<int N> __device__ __forceinline__ void fence_regs(float* r) {
    #pragma unroll
    for (int i = 0; i < N; i++) asm volatile("" : "+f"(r[i]) :: "memory");
}
template<int N> __device__ __forceinline__ void fence_regs_u(uint32_t* r) {
    #pragma unroll
    for (int i = 0; i < N; i++) asm volatile("" : "+r"(r[i]) :: "memory");
}
__device__ __forceinline__ uint32_t pack_bf16(float lo, float hi) {
    uint32_t r; asm("cvt.rn.bf16x2.f32 %0, %1, %2;" : "=r"(r) : "f"(hi), "f"(lo)); return r;
}
__device__ __forceinline__ float bf_lo(uint32_t v) { return __uint_as_float(v << 16); }
__device__ __forceinline__ float bf_hi(uint32_t v) { return __uint_as_float(v & 0xFFFF0000u); }

__device__ __forceinline__ void wgmma_ss_n128_t(float* d, uint64_t da, uint64_t db, int scale_d) {
    asm volatile("{\n.reg .pred p;\nsetp.ne.b32 p, %66, 0;\n"
        "wgmma.mma_async.sync.aligned.m64n128k16.f32.bf16.bf16 {%0,%1,%2,%3,%4,%5,%6,%7,%8,%9,%10,%11,%12,%13,%14,%15,%16,%17,%18,%19,%20,%21,%22,%23,%24,%25,%26,%27,%28,%29,%30,%31,%32,%33,%34,%35,%36,%37,%38,%39,%40,%41,%42,%43,%44,%45,%46,%47,%48,%49,%50,%51,%52,%53,%54,%55,%56,%57,%58,%59,%60,%61,%62,%63}, %64, %65, p, 1, 1, 0, 1;\n}"
        : "+f"(d[0]), "+f"(d[1]), "+f"(d[2]), "+f"(d[3]), "+f"(d[4]), "+f"(d[5]), "+f"(d[6]), "+f"(d[7]), "+f"(d[8]), "+f"(d[9]), "+f"(d[10]), "+f"(d[11]), "+f"(d[12]), "+f"(d[13]), "+f"(d[14]), "+f"(d[15]), "+f"(d[16]), "+f"(d[17]), "+f"(d[18]), "+f"(d[19]), "+f"(d[20]), "+f"(d[21]), "+f"(d[22]), "+f"(d[23]), "+f"(d[24]), "+f"(d[25]), "+f"(d[26]), "+f"(d[27]), "+f"(d[28]), "+f"(d[29]), "+f"(d[30]), "+f"(d[31]), "+f"(d[32]), "+f"(d[33]), "+f"(d[34]), "+f"(d[35]), "+f"(d[36]), "+f"(d[37]), "+f"(d[38]), "+f"(d[39]), "+f"(d[40]), "+f"(d[41]), "+f"(d[42]), "+f"(d[43]), "+f"(d[44]), "+f"(d[45]), "+f"(d[46]), "+f"(d[47]), "+f"(d[48]), "+f"(d[49]), "+f"(d[50]), "+f"(d[51]), "+f"(d[52]), "+f"(d[53]), "+f"(d[54]), "+f"(d[55]), "+f"(d[56]), "+f"(d[57]), "+f"(d[58]), "+f"(d[59]), "+f"(d[60]), "+f"(d[61]), "+f"(d[62]), "+f"(d[63])
        : "l"(da), "l"(db), "r"(scale_d));
}
__device__ __forceinline__ void wgmma_ss_n96_t(float* d, uint64_t da, uint64_t db, int scale_d) {
    asm volatile("{\n.reg .pred p;\nsetp.ne.b32 p, %50, 0;\n"
        "wgmma.mma_async.sync.aligned.m64n96k16.f32.bf16.bf16 {%0,%1,%2,%3,%4,%5,%6,%7,%8,%9,%10,%11,%12,%13,%14,%15,%16,%17,%18,%19,%20,%21,%22,%23,%24,%25,%26,%27,%28,%29,%30,%31,%32,%33,%34,%35,%36,%37,%38,%39,%40,%41,%42,%43,%44,%45,%46,%47}, %48, %49, p, 1, 1, 0, 1;\n}"
        : "+f"(d[0]), "+f"(d[1]), "+f"(d[2]), "+f"(d[3]), "+f"(d[4]), "+f"(d[5]), "+f"(d[6]), "+f"(d[7]), "+f"(d[8]), "+f"(d[9]), "+f"(d[10]), "+f"(d[11]), "+f"(d[12]), "+f"(d[13]), "+f"(d[14]), "+f"(d[15]), "+f"(d[16]), "+f"(d[17]), "+f"(d[18]), "+f"(d[19]), "+f"(d[20]), "+f"(d[21]), "+f"(d[22]), "+f"(d[23]), "+f"(d[24]), "+f"(d[25]), "+f"(d[26]), "+f"(d[27]), "+f"(d[28]), "+f"(d[29]), "+f"(d[30]), "+f"(d[31]), "+f"(d[32]), "+f"(d[33]), "+f"(d[34]), "+f"(d[35]), "+f"(d[36]), "+f"(d[37]), "+f"(d[38]), "+f"(d[39]), "+f"(d[40]), "+f"(d[41]), "+f"(d[42]), "+f"(d[43]), "+f"(d[44]), "+f"(d[45]), "+f"(d[46]), "+f"(d[47])
        : "l"(da), "l"(db), "r"(scale_d));
}
__device__ __forceinline__ void wgmma_ss_n64_t(float* d, uint64_t da, uint64_t db, int scale_d) {
    asm volatile("{\n.reg .pred p;\nsetp.ne.b32 p, %34, 0;\n"
        "wgmma.mma_async.sync.aligned.m64n64k16.f32.bf16.bf16 {%0,%1,%2,%3,%4,%5,%6,%7,%8,%9,%10,%11,%12,%13,%14,%15,%16,%17,%18,%19,%20,%21,%22,%23,%24,%25,%26,%27,%28,%29,%30,%31}, %32, %33, p, 1, 1, 0, 1;\n}"
        : "+f"(d[0]), "+f"(d[1]), "+f"(d[2]), "+f"(d[3]), "+f"(d[4]), "+f"(d[5]), "+f"(d[6]), "+f"(d[7]), "+f"(d[8]), "+f"(d[9]), "+f"(d[10]), "+f"(d[11]), "+f"(d[12]), "+f"(d[13]), "+f"(d[14]), "+f"(d[15]), "+f"(d[16]), "+f"(d[17]), "+f"(d[18]), "+f"(d[19]), "+f"(d[20]), "+f"(d[21]), "+f"(d[22]), "+f"(d[23]), "+f"(d[24]), "+f"(d[25]), "+f"(d[26]), "+f"(d[27]), "+f"(d[28]), "+f"(d[29]), "+f"(d[30]), "+f"(d[31])
        : "l"(da), "l"(db), "r"(scale_d));
}
__device__ __forceinline__ void wgmma_ss_n40_k(float* d, uint64_t da, uint64_t db, int scale_d) {
    asm volatile("{\n.reg .pred p;\nsetp.ne.b32 p, %22, 0;\n"
        "wgmma.mma_async.sync.aligned.m64n40k16.f32.bf16.bf16 {%0,%1,%2,%3,%4,%5,%6,%7,%8,%9,%10,%11,%12,%13,%14,%15,%16,%17,%18,%19}, %20, %21, p, 1, 1, 0, 0;\n}"
        : "+f"(d[0]), "+f"(d[1]), "+f"(d[2]), "+f"(d[3]), "+f"(d[4]), "+f"(d[5]), "+f"(d[6]), "+f"(d[7]), "+f"(d[8]), "+f"(d[9]), "+f"(d[10]), "+f"(d[11]), "+f"(d[12]), "+f"(d[13]), "+f"(d[14]), "+f"(d[15]), "+f"(d[16]), "+f"(d[17]), "+f"(d[18]), "+f"(d[19])
        : "l"(da), "l"(db), "r"(scale_d));
}
__device__ __forceinline__ void wgmma_rs_n64_z(float* d, uint32_t a0, uint32_t a1, uint32_t a2, uint32_t a3, uint64_t db) {
    asm volatile("{\n.reg .pred p;\nsetp.ne.b32 p, 0, 0;\n"
        "wgmma.mma_async.sync.aligned.m64n64k16.f32.bf16.bf16 {%0,%1,%2,%3,%4,%5,%6,%7,%8,%9,%10,%11,%12,%13,%14,%15,%16,%17,%18,%19,%20,%21,%22,%23,%24,%25,%26,%27,%28,%29,%30,%31}, {%32,%33,%34,%35}, %36, p, 1, 1, 0;\n}"
        : "+f"(d[0]), "+f"(d[1]), "+f"(d[2]), "+f"(d[3]), "+f"(d[4]), "+f"(d[5]), "+f"(d[6]), "+f"(d[7]), "+f"(d[8]), "+f"(d[9]), "+f"(d[10]), "+f"(d[11]), "+f"(d[12]), "+f"(d[13]), "+f"(d[14]), "+f"(d[15]), "+f"(d[16]), "+f"(d[17]), "+f"(d[18]), "+f"(d[19]), "+f"(d[20]), "+f"(d[21]), "+f"(d[22]), "+f"(d[23]), "+f"(d[24]), "+f"(d[25]), "+f"(d[26]), "+f"(d[27]), "+f"(d[28]), "+f"(d[29]), "+f"(d[30]), "+f"(d[31])
        : "r"(a0), "r"(a1), "r"(a2), "r"(a3), "l"(db));
}
__device__ __forceinline__ void wgmma_rs_n24_t(float* d, uint32_t a0, uint32_t a1, uint32_t a2, uint32_t a3, uint64_t db) {
    asm volatile("{\n.reg .pred p;\nsetp.ne.b32 p, 1, 0;\n"
        "wgmma.mma_async.sync.aligned.m64n24k16.f32.bf16.bf16 {%0,%1,%2,%3,%4,%5,%6,%7,%8,%9,%10,%11}, {%12,%13,%14,%15}, %16, p, 1, 1, 1;\n}"
        : "+f"(d[0]), "+f"(d[1]), "+f"(d[2]), "+f"(d[3]), "+f"(d[4]), "+f"(d[5]), "+f"(d[6]), "+f"(d[7]), "+f"(d[8]), "+f"(d[9]), "+f"(d[10]), "+f"(d[11])
        : "r"(a0), "r"(a1), "r"(a2), "r"(a3), "l"(db));
}

__device__ __forceinline__ uint32_t exp_mufu(float x0, float x1) {
    float e0, e1;
    asm("ex2.approx.ftz.f32 %0, %1;" : "=f"(e0) : "f"(x0));
    asm("ex2.approx.ftz.f32 %0, %1;" : "=f"(e1) : "f"(x1));
    return pack_bf16(e0, e1);
}
__device__ __forceinline__ uint32_t exp_emu(float t0, float t1, uint32_t kone, uint32_t ka2) {
    const uint32_t u = __float_as_uint(t1) * 65536u + __float_as_uint(t0);
    uint32_t m, w, q;
    asm("lop3.b32 %0, %1, 0x007F007F, %2, 0xEA;" : "=r"(m) : "r"(u), "r"(kone));
    asm("fma.rn.bf16x2 %0, %1, %2, %3;" : "=r"(w) : "r"(m), "r"(ka2), "r"(0xBD07BD07u));
    asm("fma.rn.bf16x2 %0, %1, %2, %3;" : "=r"(q) : "r"(w), "r"(m), "r"(0x3F323F32u));
    return u + q - m;
}
__device__ __forceinline__ void softmax_fast(const float* s, uint32_t* p, uint32_t kone, uint32_t ka2) {
    #pragma unroll
    for (int i = 0; i < 16; i++) p[i] = (i >= 10) ? exp_mufu(s[2 * i], s[2 * i + 1]) : exp_emu(s[2 * i], s[2 * i + 1], kone, ka2);
}

constexpr uint64_t VD_CHUNK = 256ull - (128ull << 32);
__device__ __forceinline__ void pv_step(float* o, const uint32_t* p, uint64_t vd) {
    #pragma unroll
    for (int k = 0; k < 4; k++) wgmma_rs_n24_t(o, p[4 * k], p[4 * k + 1], p[4 * k + 2], p[4 * k + 3], vd + (uint64_t)(k * 16));
}
__device__ __forceinline__ uint64_t k_desc(uint64_t kdA, uint64_t kdC, int t) { return t < 16 ? kdA + (uint64_t)(t * 256) : kdC + (uint64_t)((t - 16) * 128); }

__device__ __forceinline__ void att_store(const float* o, int row0, int h, int gq, int c) {
    const float r0 = 1.f / o[8], r1 = 1.f / o[10];
    __nv_bfloat16* op = g_o + (size_t)(row0 + gq) * D_ + h * 16 + c * 2;
    *reinterpret_cast<uint32_t*>(op) = pack_bf16(o[0] * r0, o[1] * r0);
    *reinterpret_cast<uint32_t*>(op + 8) = pack_bf16(o[4] * r0, o[5] * r0);
    *reinterpret_cast<uint32_t*>(op + 8 * D_) = pack_bf16(o[2] * r1, o[3] * r1);
    *reinterpret_cast<uint32_t*>(op + 8 * D_ + 8) = pack_bf16(o[6] * r1, o[7] * r1);
}

constexpr int KB_ONES = 131072, KB_RING = 133120, KB_SMEM = KB_RING + 98304;
constexpr int P1_STAGE = 40960, KB_STATS = 229376, KB_CS = KB_STATS + 1024, KB_QKVST = 0, KB_LNST = 5 * P1_STAGE;

struct WPtrs { const void *wg, *wu, *wd, *wo; };
struct KBParams {
    CUtensorMap tm_x, tm_wqkv2, tm_wqkv1, tm_qst, tm_kvst, tm_xn, tm_wg, tm_wu, tm_h, tm_wd, tm_o, tm_wo, tm_out;
};

__device__ __forceinline__ uint32_t kv_bar_idx(int c) { return c < 8 ? (c >> 1) : 4 + ((c - 8) >> 2); }

__device__ __forceinline__ void att_segment(const uint32_t* q, float* o, uint64_t kdA, uint64_t kdC, uint64_t vd, uint32_t kvbar, bool first, int c0, int c1, uint32_t kone, uint32_t ka2, uint64_t mA, uint64_t mB) {
    float s[32]; uint32_t pa[16], pb[16];
    #pragma unroll
    for (int i = 0; i < 32; i++) s[i] = 0.f;
    vd += (uint64_t)c0 * VD_CHUNK;
    uint64_t kd = k_desc(kdA, kdC, 2 * c0);
    uint64_t kst = (c0 < 8) ? 256 : 128;
    if (first) mbar_wait(kvbar, 0);
    fence_regs<12>(o); fence_regs<32>(s);
    wg_fence();
    wgmma_rs_n64_z(s, q[0], q[1], q[2], q[3], kd);
    wgmma_ss_n40_k(s, mA, mB, 1);
    wg_commit();
    wg_wait<0>();
    fence_regs<32>(s);
    softmax_fast(s, pa, kone, ka2);
    auto step = [&](uint32_t* pc, uint32_t* pn, uint64_t kdn, uint64_t vdc) {
        fence_regs_u<16>(pc); fence_regs<32>(s);
        wg_fence();
        wgmma_rs_n64_z(s, q[0], q[1], q[2], q[3], kdn);
        wgmma_ss_n40_k(s, mA, mB, 1);
        wg_commit();
        pv_step(o, pc, vdc);
        wg_commit();
        wg_wait<1>();
        fence_regs<32>(s);
        softmax_fast(s, pn, kone, ka2);
        fence_regs_u<16>(pn);
    };
    #pragma unroll 1
    for (int ch = c0; ch < c1 - 1; ch++) {
        step(pa, pb, kd + kst, vd);
        kd += 2 * kst;
        if (ch == 7) { kd = kdC; kst = 128; }
        if (first) mbar_wait(kvbar + kv_bar_idx(ch + 1) * 8, 0);
        step(pb, pa, kd, vd + 64);
        vd += VD_CHUNK;
    }
    step(pa, pb, kd + kst, vd);
    fence_regs_u<16>(pb);
    wg_fence();
    pv_step(o, pb, vd + 64);
    wg_commit();
    wg_wait<0>();
    fence_regs<12>(o);
}

__device__ __forceinline__ void load_q(uint32_t* q, const uint8_t* qp) {
    q[0] = __ldcg(reinterpret_cast<const uint32_t*>(qp));       q[1] = __ldcg(reinterpret_cast<const uint32_t*>(qp + 256));
    q[2] = __ldcg(reinterpret_cast<const uint32_t*>(qp + 128)); q[3] = __ldcg(reinterpret_cast<const uint32_t*>(qp + 384));
}

__global__ void __cluster_dims__(2, 1, 1) __launch_bounds__(512, 1) k_main(const __grid_constant__ KBParams P, const __nv_bfloat16* __restrict__ x,
                                                 const __nv_bfloat16* __restrict__ wqkv, const WPtrs W, __nv_bfloat16* __restrict__ out) {
    extern __shared__ __align__(1024) uint8_t smem[];
    __shared__ __align__(8) uint64_t wq_full[5], wq_empty[5], cta_bar[1], pair_bar[2], kv_bar[6], gu_full[3], dn_full[4];
    __shared__ uint32_t s_safe, s_epoch;
    __shared__ __align__(128) uint32_t s_magic[128];
    const uint32_t sb = smem_u32(smem), ring = sb + KB_RING;
    const int crank = blockIdx.x & 1;
    const int r = (blockIdx.x >> 4) * 2 + crank, g = (blockIdx.x >> 1) & 7;
    const int r3 = blockIdx.x >> 3, g3 = blockIdx.x & 7;
    const int tid = (threadIdx.x + 384) & 511;
    const int warp_id = __shfl_sync(0xffffffff, tid >> 5, 0);
    const int wg = warp_id >> 2, warp = warp_id & 3;
    const int np = (g < 6) ? 3 : 2, ct0 = (g < 6) ? 3 * g : 18 + 2 * (g - 6);
    auto issue_gu = [&](int it, int s) {
        const uint32_t slot = ring + s * 32768, bar = smem_u32(&gu_full[0]) + s * 8;
        const int col = (ct0 + (it >> 3)) * 64, k0 = (it & 7) * 64;
        if (warp_id == 12) { if (elect_one()) { mbar_expect_tx(bar, 32768); tma2d(slot, &P.tm_xn, k0, r * 128, bar); } }
        else if (warp_id == 13) { if (elect_one()) tma2d(slot + 16384, &P.tm_wg, col, k0, bar); }
        else if (warp_id == 14) { if (elect_one()) tma2d(slot + 24576, &P.tm_wu, col, k0, bar); }
        __syncwarp();
    };

    {
        const int lane = tid & 31, gq = lane >> 2, c = lane & 3;
        const int mi = wg >> 1, ni = wg & 1;
        float2* s_stats = reinterpret_cast<float2*>(smem + KB_STATS);
        const uint32_t wf = smem_u32(&wq_full[0]), we = smem_u32(&wq_empty[0]);
        auto issue_w = [&](int kb, int sl) {
            const uint32_t dst = sb + sl * P1_STAGE + 16384 + crank * 12288, bar = wf + sl * 8;
            tma3d_mc(dst, &P.tm_wqkv2, 0, kb * 64, crank * 32 + g * 2, bar, (uint16_t)3);
            tma3d_mc(dst + 8192, &P.tm_wqkv1, 0, kb * 64, 16 + g * 2 + crank, bar, (uint16_t)3);
        };
        auto issue_stage = [&](int kb, int sl) {
            mbar_expect_tx(wf + sl * 8, P1_STAGE);
            tma2d(sb + sl * P1_STAGE, &P.tm_x, kb * 64, r * 128, wf + sl * 8);
            issue_w(kb, sl);
        };
        uint32_t epoch = 0;
        if ((tid & 127) == 0) asm volatile("ld.global.cg.u32 %0, [%1];" : "=r"(epoch) : "l"(&g_epoch));
        if (warp_id == 15 && lane < 2) {
            if (lane == 0) l2_prefetch(reinterpret_cast<const uint8_t*>(x) + (size_t)blockIdx.x * 16384, 16384);
            else l2_prefetch(reinterpret_cast<const uint8_t*>(wqkv) + (size_t)blockIdx.x * 12288, 12288);
        }
        const int lrow = r * 128 + g * 16 + warp_id;
        uint32_t xw[8], wv[32];
        asm volatile("ld.global.nc.v4.u32 {%0,%1,%2,%3}, [%4];" : "=r"(xw[0]), "=r"(xw[1]), "=r"(xw[2]), "=r"(xw[3]) : "l"(x + (size_t)lrow * D_ + lane * 8));
        asm volatile("ld.global.nc.v4.u32 {%0,%1,%2,%3}, [%4];" : "=r"(xw[4]), "=r"(xw[5]), "=r"(xw[6]), "=r"(xw[7]) : "l"(x + (size_t)lrow * D_ + 256 + lane * 8));
        if (warp_id < 3) {
            const __nv_bfloat16* wp = wqkv + (size_t)(r * 32) * (3 * D_) + warp_id * 512 + g * 64 + lane * 2;
            #pragma unroll
            for (int i = 0; i < 32; i++) asm volatile("ld.global.nc.u32 %0, [%1];" : "=r"(wv[i]) : "l"(wp + i * (3 * D_)));
        }
        {
            #pragma unroll
            for (int i = 0; i < 2; i++) {
                const int idx = tid + i * 512, row = idx >> 3, ch = idx & 7;
                asm volatile("cp.async.cg.shared.global [%0], [%1], 16;" :: "r"(sb + row * 128 + ((ch ^ (row & 7)) << 4)), "l"(x + (size_t)(r * 128 + row) * D_ + ch * 8) : "memory");
            }
            #pragma unroll
            for (int i = 0; i < 3; i++) {
                const int idx = tid + i * 512, at = idx >> 8, row = (idx >> 2) & 63, ch = idx & 3;
                const int col = (at == 2 ? 512 : at == 5 ? 512 + 32 : at < 2 ? at * 32 : 1024 + (at - 3) * 32) + g * 64;
                asm volatile("cp.async.cg.shared.global [%0], [%1], 16;" :: "r"(sb + 16384 + at * 4096 + row * 64 + ((ch ^ ((row >> 1) & 3)) << 4)), "l"(wqkv + (size_t)row * (3 * D_) + col + ch * 8) : "memory");
            }
            asm volatile("cp.async.commit_group;" ::: "memory");
        }
        if (warp_id == 13) {
            if (elect_one()) {
                mbar_init(wf + 8, 1);
                asm volatile("fence.mbarrier_init.release.cluster;" ::: "memory");
                fence_async_smem();
                mbar_expect_tx(wf + 8, P1_STAGE);
                tma2d(sb + P1_STAGE, &P.tm_x, 64, r * 128, wf + 8);
            }
        } else if (tid == 0) {
            TS_MIN(0);
            mbar_init(wf, 1);
            for (int i = 2; i < 5; i++) mbar_init(wf + i * 8, 1);
            for (int i = 0; i < 5; i++) mbar_init(we + i * 8, 8);
            for (int i = 0; i < 3; i++) mbar_init(smem_u32(&gu_full[i]), 1);
            for (int i = 0; i < 4; i++) mbar_init(smem_u32(&dn_full[i]), 1);
            for (int i = 0; i < 6; i++) mbar_init(smem_u32(&kv_bar[i]), 1);
            mbar_init(smem_u32(&cta_bar[0]), 16); mbar_init(smem_u32(&pair_bar[0]), 2); mbar_init(smem_u32(&pair_bar[1]), 2);
            asm volatile("fence.mbarrier_init.release.cluster;" ::: "memory");
        } else if (warp_id == 14) {
            if (lane < 10) asm volatile("prefetch.tensormap [%0];" :: "l"(&P.tm_qst + lane) : "memory");
        }
        __syncthreads();
        asm volatile("barrier.cluster.arrive.relaxed.aligned;\nbarrier.cluster.wait.aligned;" ::: "memory");
        if (warp_id == 12 || warp_id == 13) { if (elect_one()) { if (warp_id == 13) issue_w(1, 1); issue_stage(warp_id - 10, warp_id - 10); if (warp_id == 12) issue_stage(4, 4); } }

        {
            float v[16];
            #pragma unroll
            for (int i = 0; i < 8; i++) { v[2 * i] = bf_lo(xw[i]); v[2 * i + 1] = bf_hi(xw[i]); }
            float s = ((v[0] + v[1]) + (v[2] + v[3])) + ((v[4] + v[5]) + (v[6] + v[7])) + (((v[8] + v[9]) + (v[10] + v[11])) + ((v[12] + v[13]) + (v[14] + v[15])));
            #pragma unroll
            for (int o = 16; o; o >>= 1) s += __shfl_xor_sync(0xffffffff, s, o);
            const float mean = s * (1.f / D_);
            float q0 = 0.f, q1 = 0.f, q2 = 0.f, q3 = 0.f;
            #pragma unroll
            for (int i = 0; i < 4; i++) {
                v[4 * i] -= mean; v[4 * i + 1] -= mean; v[4 * i + 2] -= mean; v[4 * i + 3] -= mean;
                q0 = fmaf(v[4 * i], v[4 * i], q0); q1 = fmaf(v[4 * i + 1], v[4 * i + 1], q1); q2 = fmaf(v[4 * i + 2], v[4 * i + 2], q2); q3 = fmaf(v[4 * i + 3], v[4 * i + 3], q3);
            }
            float q = (q0 + q1) + (q2 + q3);
            #pragma unroll
            for (int o = 16; o; o >>= 1) q += __shfl_xor_sync(0xffffffff, q, o);
            const float rstd = rsqrtf(q * (1.f / D_) + 1e-5f);
            uint4* d = reinterpret_cast<uint4*>(smem + KB_LNST + warp_id * 1024);
            d[lane] = make_uint4(pack_bf16(v[0] * rstd, v[1] * rstd), pack_bf16(v[2] * rstd, v[3] * rstd), pack_bf16(v[4] * rstd, v[5] * rstd), pack_bf16(v[6] * rstd, v[7] * rstd));
            d[lane + 32] = make_uint4(pack_bf16(v[8] * rstd, v[9] * rstd), pack_bf16(v[10] * rstd, v[11] * rstd), pack_bf16(v[12] * rstd, v[13] * rstd), pack_bf16(v[14] * rstd, v[15] * rstd));
            if (lane == 0) *reinterpret_cast<float2*>(smem + KB_LNST + 16384 + warp_id * 8) = make_float2(mean, rstd);
            fence_async_smem();
            __syncwarp();
            if (lane == 0) mbar_arrive(smem_u32(&cta_bar[0]));
        }
        float acc[48];
        #pragma unroll
        for (int i = 0; i < 48; i++) acc[i] = 0.f;
        const uint64_t dA0 = make_desc(sb + mi * 8192, 16, 1024, 1);
        const uint64_t dB = make_desc(sb + 16384 + ni * 12288, 4096, 512, 2);
        #pragma unroll
        for (int kb = 0; kb < 8; kb++) {
            constexpr int SU = P1_STAGE / 16;
            const int sl = kb % 5;
            if (kb == 0) { asm volatile("cp.async.wait_group 0;" ::: "memory"); fence_async_smem(); __syncthreads(); }
            else mbar_wait(wf + sl * 8, (kb == 5) ? 0 : kb / 5);
            fence_regs<48>(acc);
            wg_fence();
            #pragma unroll
            for (int k = 0; k < 4; k++) wgmma_ss_n96_t(acc, dA0 + (uint64_t)(sl * SU + k * 2), dB + (uint64_t)(sl * SU + k * 64), 1);
            wg_commit();
            if (tid == 0 && (kb == 0 || kb == 7)) TS_BOTH(20 + kb);
            if (kb == 0 && warp_id == 15) {
                mbar_wait(smem_u32(&cta_bar[0]), 0);
                if (lane == 0) bulk_store(g_xn + (size_t)(r * 128 + g * 16) * D_, sb + KB_LNST, 16384);
                else if (lane == 1) bulk_store(g_stats + r * 128 + g * 16, sb + KB_LNST + 16384, 128);
                asm volatile("cp.async.bulk.commit_group;" ::: "memory");
            }
            if (kb == 2 && warp_id == 15) {
                asm volatile("cp.async.bulk.wait_group 0;" ::: "memory");
                fence_async();
                __syncwarp();
                if (lane == 0) { flag_add_relaxed(&g_flags.ln[r]); TS_BOTH(1); }
                __syncwarp();
            }
            if (kb == 2 && warp_id < 3) {
                float cs0 = 0.f, cs1 = 0.f, cs2 = 0.f, cs3 = 0.f;
                #pragma unroll
                for (int i = 0; i < 16; i++) { cs0 += bf_lo(wv[i]); cs1 += bf_hi(wv[i]); cs2 += bf_lo(wv[16 + i]); cs3 += bf_hi(wv[16 + i]); }
                *reinterpret_cast<float2*>(smem + KB_LNST + 16384 + 128 + (warp_id * 64 + lane * 2) * 4) = make_float2(cs0 + cs2, cs1 + cs3);
                fence_async_smem();
                __syncwarp();
                if (lane == 0) bulk_store(g_csp + (g * 16 + r) * 192 + warp_id * 64, sb + KB_LNST + 16384 + 128 + warp_id * 256, 256);
                asm volatile("cp.async.bulk.commit_group;" ::: "memory");
            }
            if (kb == 4 && warp_id < 3) {
                asm volatile("cp.async.bulk.wait_group 0;" ::: "memory");
                fence_async();
                __syncwarp();
                if (lane == 0) flag_add_relaxed(&g_flags.cs[g]);
                __syncwarp();
            }
            if (kb >= 1 && kb <= 3) {
                wg_wait<1>();
                if (warp == 0) { if (elect_one()) arrive_pair(we + (kb - 1) * 8); }
                if (warp_id == 13) { if (elect_one()) { mbar_wait_cluster(we + (kb - 1) * 8, 0); issue_stage(kb + 4, kb - 1); } }
            }
            if (kb == 7) {
                if (warp_id < 4) {
                    if (tid == 0) { s_epoch = epoch + 1; flag_wait(&g_flags.ln[r], 8 * (epoch + 1)); }
                    bar_sync(6, 128);
                    s_stats[tid] = __ldcg(&g_stats[r * 128 + tid]);
                } else if (warp_id < 10) {
                    if (tid == 128) flag_wait(&g_flags.cs[g], 48 * (epoch + 1));
                    bar_sync(7, 192);
                    float t = 0.f;
                    #pragma unroll
                    for (int i = 0; i < 16; i++) t += __ldcg(&g_csp[(g * 16 + i) * 192 + tid - 128]);
                    *reinterpret_cast<float*>(smem + KB_CS + (tid - 128) * 4) = t;
                }
            }
        }
        wg_wait<0>();
        fence_regs<48>(acc);
        __syncthreads();
        if (tid == 0) TS_BOTH(3);
        if (wg == 3) { fence_async(); issue_gu(0, 0); issue_gu(1, 1); }
        const int rl = mi * 64 + warp * 16;
        const float2 st0 = s_stats[rl + gq], st1 = s_stats[rl + gq + 8];
        const float* cs = reinterpret_cast<const float*>(smem + KB_CS);
        {
            const int gl = rl >> 3;
            uint8_t* stg = smem + KB_QKVST + gq * 16 + c * 4;
            uint8_t* pk = stg + (2 + (gl >> 3)) * 8192 + (gl & 7) * 256;
            uint8_t* p64 = ni ? stg + 4 * 8192 + gl * 128 : stg + (gl >> 3) * 8192 + (gl & 7) * 256;
            const uint32_t s_db = ni ? 8192u : 128u, s_hf = ni ? 128u : 256u;
            const float qs = ni ? 1.f : QSCALE;
            const float m0 = st0.x, m1 = st1.x, r0 = st0.y, r1 = st1.y;
            #pragma unroll
            for (int j = 0; j < 12; j++) {
                const int t8 = (j < 8) ? j : ni * 4 + (j - 8);
                const float2 cv = *reinterpret_cast<const float2*>(cs + ((j < 8) ? ni * 128 : 64) + t8 * 8 + c * 2);
                const float f0 = (j < 8) ? r0 * qs : r0, f1 = (j < 8) ? r1 * qs : r1;
                acc[4 * j + 0] = (acc[4 * j + 0] - m0 * cv.x) * f0;
                acc[4 * j + 1] = (acc[4 * j + 1] - m0 * cv.y) * f0;
                acc[4 * j + 2] = (acc[4 * j + 2] - m1 * cv.x) * f1;
                acc[4 * j + 3] = (acc[4 * j + 3] - m1 * cv.y) * f1;
                uint8_t* p; uint32_t hfs;
                if (j < 8) { p = p64 + (j >> 1) * 2048 + (j & 1) * s_db; hfs = s_hf; }
                else { p = pk + (t8 >> 1) * 2048 + (t8 & 1) * 128; hfs = 256; }
                *reinterpret_cast<uint32_t*>(p) = pack_bf16(acc[4 * j], acc[4 * j + 1]);
                *reinterpret_cast<uint32_t*>(p + hfs) = pack_bf16(acc[4 * j + 2], acc[4 * j + 3]);
            }
        }
        #pragma unroll
        for (int hh = 0; hh < 6; hh++) {
            if (ni == 0 || hh >= 4) {
                const float* a = acc + hh * 8;
                float n0 = a[0] * a[0] + a[1] * a[1] + a[4] * a[4] + a[5] * a[5];
                float n1 = a[2] * a[2] + a[3] * a[3] + a[6] * a[6] + a[7] * a[7];
                n0 += __shfl_xor_sync(0xffffffff, n0, 1); n1 += __shfl_xor_sync(0xffffffff, n1, 1);
                n0 += __shfl_xor_sync(0xffffffff, n0, 2); n1 += __shfl_xor_sync(0xffffffff, n1, 2);
                const uint32_t m = __reduce_max_sync(0xffffffff, max(__float_as_uint(n0), __float_as_uint(n1)));
                const int isk = (hh >= 4), hd = isk ? ni * 2 + (hh - 4) : hh;
                if (lane == 0) *reinterpret_cast<uint32_t*>(smem + KB_QKVST + 49152 + ((isk * 4 + hd) * 8 + (rl >> 4)) * 4) = m;
            }
        }
        fence_async_smem();
        __syncthreads();
        if (tid == 0) TS_BOTH(14);
        if (wg == 3) issue_gu(2, 2);
        if (warp_id == 9) {
            if (lane < 6) {
                const int off = lane < 2 ? r * 4096 + lane * 2048
                              : lane < 4 ? (r < 8 ? (2 * r + lane - 2) * 4096 + 2048 : 98304 + (r - 8) * 4096 + (lane - 2) * 2048)
                              : lane == 4 ? r * 4096 : 65536 + r * 2048;
                tma2d_store(lane < 2 ? &P.tm_qst : &P.tm_kvst, sb + KB_QKVST + lane * 8192, off >> 3, g * 4);
            } else if (lane == 6) bulk_store(g_nrm + (g * 16 + r) * 64, sb + KB_QKVST + 49152, 256);
            asm volatile("cp.async.bulk.commit_group;" ::: "memory");
            asm volatile("cp.async.bulk.wait_group 0;" ::: "memory");
            if (lane == 0) TS_BOTH(15);
            fence_async();
            __syncwarp();
            if (elect_one()) { flag_add_relaxed(&g_flags.qkv[g]); arrive_pair(smem_u32(&pair_bar[1])); TS_BOTH(4); }
            __syncwarp();
        }
    }

    if (wg < 3) {
        asm volatile("setmaxnreg.dec.sync.aligned.u32 112;");
        const int lane = opaque_tid() & 31, gq = lane >> 2, c = lane & 3;
        const int h = g * 4 + (r >> 2), qq = r & 3;
        const uint32_t kvbar = smem_u32(&kv_bar[0]);
        if (tid == 0) flag_wait(&g_flags.qkv[g], 16 * s_epoch);
        __syncwarp();
        bar_sync(1, 384);
        if (tid == 0) TS_BOTH(16);
        if (warp_id < 6) {
            fence_async();
            if (elect_one()) {
                const uint8_t* src = g_kv + h * 131072;
                const uint32_t bar = kvbar + warp_id * 8;
                mbar_expect_tx(bar, warp_id < 4 ? 24576 : 16384);
                mbar_wait_cluster(smem_u32(&pair_bar[1]), 0);
                if (warp_id < 4) {
                    if (crank == 0) bulk_load_mc(sb + warp_id * 16384, src + warp_id * 16384, 16384, bar, (uint16_t)3);
                    else bulk_load_mc(sb + 65536 + warp_id * 8192, src + 65536 + warp_id * 8192, 8192, bar, (uint16_t)3);
                } else if (crank == 1) {
                    bulk_load_mc(sb + 98304 + (warp_id - 4) * 16384, src + 98304 + (warp_id - 4) * 16384, 16384, bar, (uint16_t)3);
                }
            }
            __syncwarp();
        } else if (warp_id == 8) {
            #pragma unroll
            for (int i = 0; i < 4; i++) *reinterpret_cast<uint4*>(smem + KB_ONES + (i * 32 + lane) * 16) = make_uint4(0x3F803F80u, 0x3F803F80u, 0x3F803F80u, 0x3F803F80u);
            if (lane < 8) {
                s_magic[lane * 4 + 0] = 0x3F803F80u; s_magic[lane * 4 + 1] = 0x00003F80u; s_magic[lane * 4 + 2] = 0u; s_magic[lane * 4 + 3] = 0u;
                #pragma unroll
                for (int i = 0; i < 4; i++) s_magic[32 + lane * 4 + i] = 0u;
                s_magic[64 + lane * 4 + 0] = 0x47C0u | ((lane & 1) ? 0xC1840000u : 0x42FE0000u);
                s_magic[64 + lane * 4 + 1] = MAGIC_BIAS; s_magic[64 + lane * 4 + 2] = 0u; s_magic[64 + lane * 4 + 3] = 0u;
                #pragma unroll
                for (int i = 0; i < 4; i++) s_magic[96 + lane * 4 + i] = 0u;
            }
            fence_async_smem();
        } else if (warp_id == 9) {
            uint32_t mk = 0;
            const int hd = r >> 2;
            #pragma unroll
            for (int i = 0; i < 4; i++) mk = max(mk, __ldcg(&g_nrm[(g * 16 + i * 4 + (lane >> 3)) * 64 + (4 + hd) * 8 + (lane & 7)]));
            const uint32_t mq = __ldcg(&g_nrm[(g * 16 + qq * 4 + (lane >> 3)) * 64 + hd * 8 + (lane & 7)]);
            const float b2 = __uint_as_float(__reduce_max_sync(0xffffffff, mk)) * __uint_as_float(__reduce_max_sync(0xffffffff, mq));
            if (lane == 0) s_safe = (b2 <= 3900.f) ? 1u : 0u;
        }
        const uint8_t* qbase = g_q + h * 65536 + ((qq * 512 + warp * 16) >> 3) * 256 + gq * 16 + c * 4;
        uint32_t q[4];
        load_q(q, qbase + (wg == 0 ? 2 : wg == 1 ? 5 : 6) * 2048);
        bar_sync(1, 384);
        uint32_t kone, ka2; asm volatile("mov.b32 %0, 0x3F803F80;" : "=r"(kone)); asm volatile("mov.b32 %0, 0x3EAF3EAF;" : "=r"(ka2));
        const uint64_t kdA = make_desc(sb + 2048, 128, 256, 0), kdC = make_desc(sb + 98304, 128, 256, 0), vd0 = make_desc(sb, 128, 65536, 0);
        const uint64_t mA = make_desc(smem_u32(s_magic), 128, 0, 0), mB = make_desc(smem_u32(s_magic) + 256, MB_LBO, 0, 0);
        float4* part = g_part + (size_t)blockIdx.x * (2 * 3 * 128) + (tid & 127);
        const bool safe = __all_sync(0xffffffff, s_safe != 0);
        if (tid == 0) TS_BOTH(6);
        if (safe) {
            const int nseg = (wg == 1) ? 4 : 3;
            #pragma unroll 1
            for (int sg = 0; sg < nseg; sg++) {
                int tile, c0 = 0, c1 = 16, nxt;
                if (wg == 0) { tile = (sg == 0) ? 2 : sg - 1; if (sg == 0) c1 = 11; nxt = sg; }
                else if (wg == 1) { tile = (sg == 0) ? 5 : (sg == 1) ? 3 : (sg == 2) ? 2 : 4; if (sg == 0) c1 = 5; if (sg == 2) c0 = 11; nxt = (sg == 0) ? 3 : (sg == 1) ? 2 : 4; }
                else { tile = (sg == 2) ? 5 : sg + 6; if (sg == 2) c0 = 5; nxt = (sg == 1) ? 5 : 7; }
                fence_regs_u<4>(q);
                float o[12];
                float4* pp = part + (tile == 2 ? 384 : 0);
                if (c0 != 0) {
                    bar_sync(tile == 2 ? 5 : 4, 256);
                    #pragma unroll
                    for (int i = 0; i < 3; i++) { const float4 b = pp[i * 128]; o[4 * i] = b.x; o[4 * i + 1] = b.y; o[4 * i + 2] = b.z; o[4 * i + 3] = b.w; }
                } else {
                    #pragma unroll
                    for (int i = 0; i < 12; i++) o[i] = 0.f;
                }
                att_segment(q, o, kdA, kdC, vd0, kvbar, sg == 0, c0, c1, kone, ka2, mA, mB);
                if (sg + 1 < nseg) load_q(q, qbase + nxt * 2048);
                if (c1 == 16) {
                    att_store(o, qq * 512 + tile * 64 + warp * 16, h, gq, c);
                } else {
                    pp[0] = make_float4(o[0], o[1], o[2], o[3]); pp[128] = make_float4(o[4], o[5], o[6], o[7]); pp[256] = make_float4(o[8], o[9], o[10], o[11]);
                    __threadfence_block();
                    bar_arrive(tile == 2 ? 5 : 4, 256);
                }
            }
            if (tid == 0) TS_BOTH(7);
        } else {
            #pragma unroll 1
            for (int i = 0; i < 6; i++) mbar_wait(kvbar + i * 8, 0);
            #pragma unroll 1
            for (int tile = wg; tile < 8; tile += 3) {
                load_q(q, qbase + tile * 2048);
                float s[32], o[12]; uint32_t p[16];
                #pragma unroll
                for (int i = 0; i < 32; i++) s[i] = 0.f;
                #pragma unroll
                for (int i = 0; i < 12; i++) o[i] = 0.f;
                float m0 = -INFINITY, m1 = -INFINITY;
                #pragma unroll 1
                for (int j = 0; j < 32; j++) {
                    fence_regs<32>(s); fence_regs_u<4>(q);
                    wg_fence();
                    wgmma_rs_n64_z(s, q[0], q[1], q[2], q[3], k_desc(kdA, kdC, j));
                    wg_commit();
                    wg_wait<0>();
                    fence_regs<32>(s);
                    #pragma unroll
                    for (int i = 0; i < 8; i++) { m0 = fmaxf(m0, fmaxf(s[4 * i], s[4 * i + 1])); m1 = fmaxf(m1, fmaxf(s[4 * i + 2], s[4 * i + 3])); }
                }
                m0 = fmaxf(m0, __shfl_xor_sync(0xffffffff, m0, 1)); m0 = fmaxf(m0, __shfl_xor_sync(0xffffffff, m0, 2));
                m1 = fmaxf(m1, __shfl_xor_sync(0xffffffff, m1, 1)); m1 = fmaxf(m1, __shfl_xor_sync(0xffffffff, m1, 2));
                #pragma unroll 1
                for (int j = 0; j < 32; j++) {
                    fence_regs<32>(s); fence_regs_u<4>(q);
                    wg_fence();
                    wgmma_rs_n64_z(s, q[0], q[1], q[2], q[3], k_desc(kdA, kdC, j));
                    wg_commit();
                    wg_wait<0>();
                    fence_regs<32>(s);
                    #pragma unroll
                    for (int i = 0; i < 8; i++) {
                        p[2 * i] = exp_mufu(s[4 * i] - m0, s[4 * i + 1] - m0);
                        p[2 * i + 1] = exp_mufu(s[4 * i + 2] - m1, s[4 * i + 3] - m1);
                    }
                    fence_regs_u<16>(p); fence_regs<12>(o);
                    wg_fence();
                    pv_step(o, p, vd0 + (uint64_t)(j >> 1) * VD_CHUNK + (uint64_t)((j & 1) * 64));
                    wg_commit();
                    wg_wait<0>();
                    fence_regs<12>(o);
                }
                att_store(o, qq * 512 + tile * 64 + warp * 16, h, gq, c);
            }
        }
        bar_sync(1, 384);
        if (tid == 0) { flag_add(&g_flags.o[qq * 8 + g]); TS_MAX(5); }
    } else {
        asm volatile("setmaxnreg.inc.sync.aligned.u32 176;");
        const int lane = opaque_tid() & 31, gq = lane >> 2, c = lane & 3;
        const int n1 = np * 8;
        const uint32_t gfull = smem_u32(&gu_full[0]), dfull = smem_u32(&dn_full[0]);
        const uint64_t gA0 = make_desc(ring, 16, 1024, 1), gB0 = make_desc(ring + 16384, 8192, 1024, 1);
        int sl = 0, prev = 0; uint32_t ph = 0;
        #pragma unroll 1
        for (int ps = 0; ps < np; ps++) {
            float acc[128];
            #pragma unroll 1
            for (int kb = 0; kb < 8; kb++) {
                const int it = ps * 8 + kb;
                mbar_wait(gfull + sl * 8, ph);
                const uint64_t dA = gA0 + (uint64_t)(sl * 2048), dB = gB0 + (uint64_t)(sl * 2048);
                fence_regs<128>(acc);
                wg_fence();
                wgmma_ss_n128_t(acc, dA, dB, kb);
                wgmma_ss_n128_t(acc + 64, dA + (uint64_t)512, dB, kb);
                #pragma unroll
                for (int k = 1; k < 4; k++) {
                    wgmma_ss_n128_t(acc, dA + (uint64_t)(k * 2), dB + (uint64_t)(k * 128), 1);
                    wgmma_ss_n128_t(acc + 64, dA + (uint64_t)(512 + k * 2), dB + (uint64_t)(k * 128), 1);
                }
                wg_commit();
                wg_wait<1>();
                if (it > 0 && it + 2 < n1) issue_gu(it + 2, prev);
                prev = sl;
                if (++sl == 3) { sl = 0; ph ^= 1; }
            }
            wg_wait<0>();
            fence_regs<128>(acc);
            if (warp == 3 && lane == 0) TS_BOTH(52 + ps);
            const uint32_t slot = ring + prev * 32768;
            bar_sync(3, 128);
            #pragma unroll
            for (int mt = 0; mt < 2; mt++) {
                const float* a = acc + mt * 64;
                const int row = mt * 64 + warp * 16 + ((lane >> 3) & 1) * 8 + (lane & 7);
                #pragma unroll
                for (int jj = 0; jj < 4; jj++) {
                    uint32_t hv[4];
                    #pragma unroll
                    for (int t = 0; t < 4; t++) {
                        const int j = 2 * jj + (t >> 1), hf = t & 1;
                        const float g0 = a[4 * j + 2 * hf], g1 = a[4 * j + 2 * hf + 1];
                        hv[t] = pack_bf16(fmaxf(g0, 0.f) * a[32 + 4 * j + 2 * hf], fmaxf(g1, 0.f) * a[32 + 4 * j + 2 * hf + 1]);
                    }
                    const int chunk = 2 * jj + (lane >> 4);
                    stsm4(slot + row * 128 + ((chunk ^ (row & 7)) << 4), hv[0], hv[1], hv[2], hv[3]);
                }
            }
            fence_async_smem();
            bar_sync(3, 128);
            if (warp == 0) {
                if (elect_one()) tma2d_store(&P.tm_h, slot, (ct0 + ps) * 64, r * 128);
                asm volatile("cp.async.bulk.commit_group;" ::: "memory");
                asm volatile("cp.async.bulk.wait_group.read 0;" ::: "memory");
            }
            bar_sync(3, 128);
        }
        if (warp == 0) {
            asm volatile("cp.async.bulk.wait_group 0;" ::: "memory");
            fence_async();
            __syncwarp();
            if (elect_one()) { flag_add_relaxed(&g_flags.h[r]); TS_BOTH(10); }
        }
        float acc[64];
        #pragma unroll
        for (int i = 0; i < 64; i++) acc[i] = 0.f;
        uint32_t o_todo = 0xFF, o_rdy = 0;
        auto issue_dn = [&](int i, int s) {
            const uint32_t slot = ring + s * 24576, bar = dfull + s * 8;
            if (i < 22) {
                if (warp_id == 12) { if (elect_one()) { mbar_expect_tx(bar, 24576); tma2d(slot, &P.tm_h, i * 64, r3 * 128, bar); } }
                else if (warp_id == 13) { if (elect_one()) tma2d(slot + 16384, &P.tm_wd, g3 * 64, i * 64, bar); }
            } else if (warp_id == 12) {
                #pragma unroll 1
                for (int it = 0; (o_rdy & o_todo) == 0; it++) {
                    if (it) __nanosleep(40);
                    unsigned int v = 0;
                    if (lane < 8) asm volatile("ld.acquire.gpu.global.u32 %0, [%1];" : "=r"(v) : "l"(&g_flags.o[(r3 >> 2) * 8 + lane]) : "memory");
                    o_rdy = __ballot_sync(0xffffffff, lane < 8 && (int)(v - 4 * s_epoch) >= 0);
                    if (it > (1 << 18)) __trap();
                }
                const uint32_t ready = o_rdy & o_todo;
                const int kb = __ffs(ready) - 1;
                o_todo &= ~(1u << kb);
                fence_async();
                if (elect_one()) {
                    mbar_expect_tx(bar, 24576);
                    tma2d(slot, &P.tm_o, kb * 64, r3 * 128, bar);
                    tma2d(slot + 16384, &P.tm_wo, g3 * 64, kb * 64, bar);
                }
            }
            __syncwarp();
        };
        if (warp == 0 && lane == 0) { flag_wait(&g_flags.h[r3], 8 * s_epoch); TS_BOTH(11); }
        bar_sync(3, 128);
        fence_async();
        #pragma unroll
        for (int i = 0; i < 4; i++) issue_dn(i, i);
        const uint64_t dA0 = make_desc(ring, 16, 1024, 1), dB0 = make_desc(ring + 16384, 8192, 1024, 1);
        auto dn_stage = [&](int i, int s, uint32_t par) {
            mbar_wait(dfull + s * 8, par);
            fence_regs<64>(acc);
            wg_fence();
            #pragma unroll
            for (int k = 0; k < 4; k++) {
                wgmma_ss_n64_t(acc, dA0 + (uint64_t)(s * 1536 + k * 2), dB0 + (uint64_t)(s * 1536 + k * 128), 1);
                wgmma_ss_n64_t(acc + 32, dA0 + (uint64_t)(s * 1536 + 512 + k * 2), dB0 + (uint64_t)(s * 1536 + k * 128), 1);
            }
            wg_commit();
            wg_wait<1>();
            if (i > 0 && i + 3 < 30) issue_dn(i + 3, (s + 3) & 3);
        };
        uint32_t xres[32];
        {
            const int row0 = r3 * 128 + warp * 16 + gq;
            #pragma unroll
            for (int i = 0; i < 32; i++)
                asm volatile("ld.global.nc.u32 %0, [%1];" : "=r"(xres[i]) : "l"(x + (size_t)(row0 + (i >> 4) * 64 + (i & 1) * 8) * D_ + g3 * 64 + ((i >> 1) & 7) * 8 + c * 2));
        }
        #pragma unroll 1
        for (int i4 = 0; i4 < 7; i4++) {
            #pragma unroll
            for (int s = 0; s < 4; s++) dn_stage(i4 * 4 + s, s, i4 & 1);
        }
        dn_stage(28, 0, 1); dn_stage(29, 1, 1);
        wg_wait<0>();
        fence_regs<64>(acc);
        if (warp == 0 && lane == 0) TS_BOTH(13);
        {
            const uint32_t slot = ring + 2 * 24576;
            #pragma unroll
            for (int mt = 0; mt < 2; mt++) {
                const int row = mt * 64 + warp * 16 + ((lane >> 3) & 1) * 8 + (lane & 7);
                #pragma unroll
                for (int jj = 0; jj < 4; jj++) {
                    uint32_t hv[4];
                    #pragma unroll
                    for (int t = 0; t < 4; t++) {
                        const int j = 2 * jj + (t >> 1), hf = t & 1;
                        const uint32_t xv = xres[mt * 16 + j * 2 + hf];
                        hv[t] = pack_bf16(acc[mt * 32 + 4 * j + 2 * hf] + bf_lo(xv), acc[mt * 32 + 4 * j + 2 * hf + 1] + bf_hi(xv));
                    }
                    const int chunk = 2 * jj + (lane >> 4);
                    stsm4(slot + row * 128 + ((chunk ^ (row & 7)) << 4), hv[0], hv[1], hv[2], hv[3]);
                }
            }
            fence_async_smem();
            bar_sync(3, 128);
            if (warp == 0) {
                if (elect_one()) tma2d_store(&P.tm_out, slot, g3 * 64, r3 * 128);
                asm volatile("cp.async.bulk.commit_group;" ::: "memory");
                asm volatile("cp.async.bulk.wait_group 0;" ::: "memory");
            }
        }
        if (warp == 0 && lane == 0) {
            TS_MAX(8);
            if (blockIdx.x == 0) g_epoch = s_epoch;
        }
    }
}

typedef CUresult (*EncodeFn)(CUtensorMap*, CUtensorMapDataType, cuuint32_t, void*, const cuuint64_t*, const cuuint64_t*, const cuuint32_t*, const cuuint32_t*,
                             CUtensorMapInterleave, CUtensorMapSwizzle, CUtensorMapL2promotion, CUtensorMapFloatOOBfill);
EncodeFn g_encode = nullptr;

void make_map_atoms(CUtensorMap* m, const void* base, int rows, int cols, int atoms) {
    cuuint64_t gd[3] = {32, (cuuint64_t)rows, (cuuint64_t)(cols / 32)};
    cuuint64_t gs[2] = {(cuuint64_t)cols * 2, 64};
    cuuint32_t bd[3] = {32, 64, (cuuint32_t)atoms};
    cuuint32_t es[3] = {1, 1, 1};
    g_encode(m, CU_TENSOR_MAP_DATA_TYPE_BFLOAT16, 3, const_cast<void*>(base), gd, gs, bd, es, CU_TENSOR_MAP_INTERLEAVE_NONE,
             CU_TENSOR_MAP_SWIZZLE_64B, CU_TENSOR_MAP_L2_PROMOTION_L2_256B, CU_TENSOR_MAP_FLOAT_OOB_FILL_NONE);
}
void make_map(CUtensorMap* m, const void* base, int rows, int cols, int box_cols, int box_rows) {
    cuuint64_t gd[2] = {(cuuint64_t)cols, (cuuint64_t)rows};
    cuuint64_t gs[1] = {(cuuint64_t)cols * 2};
    cuuint32_t bd[2] = {(cuuint32_t)box_cols, (cuuint32_t)box_rows};
    cuuint32_t es[2] = {1, 1};
    g_encode(m, CU_TENSOR_MAP_DATA_TYPE_BFLOAT16, 2, const_cast<void*>(base), gd, gs, bd, es, CU_TENSOR_MAP_INTERLEAVE_NONE,
             box_cols == 64 ? CU_TENSOR_MAP_SWIZZLE_128B : CU_TENSOR_MAP_SWIZZLE_64B, CU_TENSOR_MAP_L2_PROMOTION_L2_256B, CU_TENSOR_MAP_FLOAT_OOB_FILL_NONE);
}

void make_map_img(CUtensorMap* m, void* base, int head_bytes) {
    cuuint64_t gd[2] = {(cuuint64_t)(head_bytes / 8), (cuuint64_t)H_};
    cuuint64_t gs[1] = {(cuuint64_t)head_bytes};
    cuuint32_t bd[2] = {256, 4};
    cuuint32_t es[2] = {1, 1};
    g_encode(m, CU_TENSOR_MAP_DATA_TYPE_UINT64, 2, base, gd, gs, bd, es, CU_TENSOR_MAP_INTERLEAVE_NONE,
             CU_TENSOR_MAP_SWIZZLE_NONE, CU_TENSOR_MAP_L2_PROMOTION_NONE, CU_TENSOR_MAP_FLOAT_OOB_FILL_NONE);
}

}

extern "C" void kernel_launch(void* const* d_in, const int* in_sizes, int n_in, void* d_out, int out_size) {
    const __nv_bfloat16* x = (const __nv_bfloat16*)d_in[0];
    const void* wqkv = d_in[1];
    const void* wo = d_in[2];
    const void* wg = d_in[4];
    const void* wu = d_in[5];
    const void* wd = d_in[6];
    if (!g_encode) {
        void* fn = nullptr; cudaDriverEntryPointQueryResult qr;
        cudaGetDriverEntryPoint("cuTensorMapEncodeTiled", &fn, cudaEnableDefault, &qr);
        g_encode = (EncodeFn)fn;
        cudaFuncSetAttribute(k_main, cudaFuncAttributeMaxDynamicSharedMemorySize, KB_SMEM);
    }
    void *p_xn, *p_h, *p_o, *p_q, *p_kv;
    cudaGetSymbolAddress(&p_q, g_q); cudaGetSymbolAddress(&p_kv, g_kv);
    cudaGetSymbolAddress(&p_xn, g_xn); cudaGetSymbolAddress(&p_h, g_h); cudaGetSymbolAddress(&p_o, g_o);
    KBParams P;
    make_map(&P.tm_x, x, S_, D_, 64, 128);
    make_map_atoms(&P.tm_wqkv2, wqkv, D_, 3 * D_, 2);
    make_map_atoms(&P.tm_wqkv1, wqkv, D_, 3 * D_, 1);
    make_map_img(&P.tm_qst, p_q, 65536);
    make_map_img(&P.tm_kvst, p_kv, 131072);
    make_map(&P.tm_xn, p_xn, S_, D_, 64, 128);
    make_map(&P.tm_wg, wg, D_, F_, 64, 64);
    make_map(&P.tm_wu, wu, D_, F_, 64, 64);
    make_map(&P.tm_h, p_h, S_, F_, 64, 128);
    make_map(&P.tm_wd, wd, F_, D_, 64, 64);
    make_map(&P.tm_o, p_o, S_, D_, 64, 128);
    make_map(&P.tm_wo, wo, D_, D_, 64, 64);
    make_map(&P.tm_out, d_out, S_, D_, 64, 128);
    cudaStream_t st = cudaStreamPerThread;
    WPtrs W = {wg, wu, wd, wo};
    k_main<<<128, 512, KB_SMEM, st>>>(P, x, (const __nv_bfloat16*)wqkv, W, (__nv_bfloat16*)d_out);
}
```
